```python
import torch

def _softmax(x, axis=-1):
    return torch.softmax(x, dim=axis)
def _gelu(x):
    return torch.nn.functional.gelu(x, approximate="tanh")
def _silu(x):
    return torch.nn.functional.silu(x)
def _sigmoid(x):
    return torch.sigmoid(x)
def _layernorm(x, axis=-1, eps=1e-5):
    m = x.mean(dim=axis, keepdim=True)
    v = x.var(dim=axis, keepdim=True, unbiased=False)
    return (x - m) / torch.sqrt(v + eps)
def _scatter_add(tgt, idx, src, axis=0):
    return tgt.clone().index_add_(axis, idx, src)
def _segment_sum(src, seg, n):
    out = torch.zeros((n,) + src.shape[1:], dtype=src.dtype)
    return out.index_add_(0, seg, src)
def _pad(x, pw):
    flat = tuple(v for pair in reversed(pw) for v in pair)
    return torch.nn.functional.pad(x, flat)

kernel_name = 'standalone__gqa_softmax__near_ridge'

def setup_inputs():

    _w = (lambda a: (lambda t: t.to(torch.bfloat16) if t.is_floating_point() else t)(torch.as_tensor(a)))
    B, Hq, Hkv, Sq, Sk, D = 16, 32, 4, 48, 1024, 128
    return {
        "q": _w((lambda *s: torch.randn(*s, dtype=torch.bfloat16) * 0.8)(B, Hq, Sq, D)),
        "k": _w((lambda *s: torch.randn(*s, dtype=torch.bfloat16) * 0.8)(B, Hkv, Sk, D)),
        "v": _w((lambda *s: torch.randn(*s, dtype=torch.bfloat16) * 0.05)(B, Hkv, Sk, D)),
    }

def reference(q, k, v):
    B, Hq, Sq, D = q.shape
    Hkv = k.shape[1]
    rep = Hq // Hkv
    k = (lambda x, n, axis: torch.repeat_interleave(x, n, dim=axis))(k, rep, axis=1)
    v = (lambda x, n, axis: torch.repeat_interleave(x, n, dim=axis))(v, rep, axis=1)
    scale = D ** -0.5
    scores = torch.einsum("bhqd,bhkd->bhqk", q, k) * scale
    p = _softmax(scores, axis=-1)
    return torch.einsum("bhqk,bhkd->bhqd", p, v)
```

```cpp
#include <cuda_runtime.h>
#include <cuda_bf16.h>
#include <cuda.h>
#include <stdint.h>
#include <stdio.h>

namespace {

constexpr int kB = 16, kHq = 32, kHkv = 4, kSq = 48, kSk = 1024, kD = 128;
constexpr int kGroups = kB * kHkv;
constexpr int kRowsPerGroup = (kHq / kHkv) * kSq;
constexpr int kRowsPerCta = 192;
constexpr int kBlockN = 128;
constexpr int kNumTiles = kSk / kBlockN;
constexpr int kSlots = 5;
constexpr int kTileBytes = kBlockN * kD * 2;
constexpr int kQBytes = 64 * kD * 2;
constexpr int kThreads = 512;
constexpr float kPMax = 1.0e18f, kPMin = 1.0e-18f;

constexpr int kSmemQ = 0;
constexpr int kSmemKV = 3 * kQBytes;
constexpr int kSmemBar = kSmemKV + kSlots * kTileBytes;
constexpr int kSmemTotal = kSmemBar + 256 + 1024 + 1024;

#define CONSUMER_REGS 160
#define USE_TOKEN 1
#define PV_HEAD 2
constexpr int kPvHead = PV_HEAD;
#define QK_TOKEN 1
#define DEPTH 2
#define ORDER 0
constexpr int kDepth = DEPTH;
__host__ __device__ constexpr bool unit_is_q(int u) { return ORDER == 0 ? (u == 0 || u == 2 || u == 3) : (u == 0 || u == 2 || u == 4); }
__host__ __device__ constexpr int unit_idx(int u) {
    return ORDER == 0 ? (u == 0 ? 0 : u == 1 ? 0 : u == 2 ? 1 : u == 3 ? 2 : u - 3)
                      : (u == 0 ? 0 : u == 1 ? 0 : u == 2 ? 1 : u == 3 ? 1 : u == 4 ? 2 : u - 3);
}
#define PACE 0
#define PACE0 1000
#define BURST 4
#define SPIN_LIMIT (1 << 22)

#define TRACE_PT(idx)
#define TRACE_GT(idx)
#define TRACE_DUMP()

__device__ __forceinline__ uint32_t smem_u32(const void* p) {
    return (uint32_t)__cvta_generic_to_shared(p);
}
__device__ __forceinline__ uint32_t clock32() {
    uint32_t t;
    asm volatile("mov.u32 %0, %%clock;" : "=r"(t));
    return t;
}
__device__ __forceinline__ void mbar_init(uint32_t bar, uint32_t count) {
    asm volatile("mbarrier.init.shared::cta.b64 [%0], %1;" ::"r"(bar), "r"(count));
}
__device__ __forceinline__ void mbar_expect_tx(uint32_t bar, uint32_t bytes) {
    asm volatile("mbarrier.arrive.expect_tx.shared::cta.b64 _, [%0], %1;" ::"r"(bar), "r"(bytes) : "memory");
}
__device__ __forceinline__ bool mbar_try_wait(uint32_t bar, uint32_t parity) {
    uint32_t ok;
    asm volatile(
        "{\n\t.reg .pred p;\n\t"
        "mbarrier.try_wait.parity.shared::cta.b64 p, [%1], %2;\n\t"
        "selp.u32 %0, 1, 0, p;\n\t}"
        : "=r"(ok) : "r"(bar), "r"(parity) : "memory");
    return ok != 0;
}
__device__ __forceinline__ bool mbar_test_wait(uint32_t bar, uint32_t parity) {
    uint32_t ok;
    asm volatile(
        "{\n\t.reg .pred p;\n\t"
        "mbarrier.test_wait.parity.shared::cta.b64 p, [%1], %2;\n\t"
        "selp.u32 %0, 1, 0, p;\n\t}"
        : "=r"(ok) : "r"(bar), "r"(parity) : "memory");
    return ok != 0;
}
__device__ __forceinline__ void mbar_wait(uint32_t bar, uint32_t parity) {
    if (mbar_try_wait(bar, parity)) return;
    int it = 0;
    while (!mbar_try_wait(bar, parity)) {
        if (++it > SPIN_LIMIT) break;
    }
}
__device__ __forceinline__ bool mbar_try_wait_cluster(uint32_t bar, uint32_t parity) {
    uint32_t ok;
    asm volatile(
        "{\n\t.reg .pred p;\n\t"
        "mbarrier.try_wait.parity.acquire.cluster.shared::cta.b64 p, [%1], %2;\n\t"
        "selp.u32 %0, 1, 0, p;\n\t}"
        : "=r"(ok) : "r"(bar), "r"(parity) : "memory");
    return ok != 0;
}
__device__ __forceinline__ void mbar_wait_cluster(uint32_t bar, uint32_t parity) {
    int it = 0;
    while (!mbar_try_wait_cluster(bar, parity)) {
        if (++it > SPIN_LIMIT) break;
    }
}
__device__ __forceinline__ void mbar_arrive_cluster(uint32_t bar, uint32_t cta) {
    asm volatile(
        "{\n\t.reg .b32 ra;\n\t"
        "mapa.shared::cluster.u32 ra, %0, %1;\n\t"
        "mbarrier.arrive.shared::cluster.b64 _, [ra];\n\t}"
        ::"r"(bar), "r"(cta) : "memory");
}
__device__ __forceinline__ void tma_load_2d(uint32_t dst, const CUtensorMap* map, uint32_t bar, int c0, int c1) {
    asm volatile(
        "cp.async.bulk.tensor.2d.shared::cluster.global.mbarrier::complete_tx::bytes [%0], [%1, {%3, %4}], [%2];"
        ::"r"(dst), "l"(map), "r"(bar), "r"(c0), "r"(c1) : "memory");
}
__device__ __forceinline__ void tma_load_2d_mc(uint32_t dst, const CUtensorMap* map, uint32_t bar, int c0, int c1, uint16_t mask) {
    asm volatile(
        "cp.async.bulk.tensor.2d.shared::cluster.global.mbarrier::complete_tx::bytes.multicast::cluster [%0], [%1, {%3, %4}], [%2], %5;"
        ::"r"(dst), "l"(map), "r"(bar), "r"(c0), "r"(c1), "h"(mask) : "memory");
}
__device__ __forceinline__ void tma_store_2d(const CUtensorMap* map, uint32_t src, int c0, int c1) {
    asm volatile(
        "cp.async.bulk.tensor.2d.global.shared::cta.bulk_group [%0, {%2, %3}], [%1];"
        ::"l"(map), "r"(src), "r"(c0), "r"(c1) : "memory");
}
__device__ __forceinline__ void named_sync(int id, int n) { asm volatile("bar.sync %0, %1;" ::"r"(id), "r"(n) : "memory"); }
__device__ __forceinline__ void named_arrive(int id, int n) { asm volatile("bar.arrive %0, %1;" ::"r"(id), "r"(n) : "memory"); }

__device__ __forceinline__ void wgmma_fence() { asm volatile("wgmma.fence.sync.aligned;" ::: "memory"); }
__device__ __forceinline__ void wgmma_commit() { asm volatile("wgmma.commit_group.sync.aligned;" ::: "memory"); }
template <int N>
__device__ __forceinline__ void wgmma_wait() { asm volatile("wgmma.wait_group.sync.aligned %0;" ::"n"(N) : "memory"); }

constexpr uint32_t kDescHi = (1024u >> 4) | (1u << 30);
__device__ __forceinline__ uint32_t desc_lo(uint32_t addr, uint32_t lbo_bytes) {
    return ((addr & 0x3FFFF) >> 4) | ((lbo_bytes >> 4) << 16);
}
__device__ __forceinline__ uint64_t mk_desc(uint32_t lo) {
    return ((uint64_t)kDescHi << 32) | (uint64_t)lo;
}

#define ACC64(d)                                                                                   \
    "+f"(d[0]), "+f"(d[1]), "+f"(d[2]), "+f"(d[3]), "+f"(d[4]), "+f"(d[5]), "+f"(d[6]), "+f"(d[7]),       \
    "+f"(d[8]), "+f"(d[9]), "+f"(d[10]), "+f"(d[11]), "+f"(d[12]), "+f"(d[13]), "+f"(d[14]), "+f"(d[15]), \
    "+f"(d[16]), "+f"(d[17]), "+f"(d[18]), "+f"(d[19]), "+f"(d[20]), "+f"(d[21]), "+f"(d[22]), "+f"(d[23]), \
    "+f"(d[24]), "+f"(d[25]), "+f"(d[26]), "+f"(d[27]), "+f"(d[28]), "+f"(d[29]), "+f"(d[30]), "+f"(d[31]), \
    "+f"(d[32]), "+f"(d[33]), "+f"(d[34]), "+f"(d[35]), "+f"(d[36]), "+f"(d[37]), "+f"(d[38]), "+f"(d[39]), \
    "+f"(d[40]), "+f"(d[41]), "+f"(d[42]), "+f"(d[43]), "+f"(d[44]), "+f"(d[45]), "+f"(d[46]), "+f"(d[47]), \
    "+f"(d[48]), "+f"(d[49]), "+f"(d[50]), "+f"(d[51]), "+f"(d[52]), "+f"(d[53]), "+f"(d[54]), "+f"(d[55]), \
    "+f"(d[56]), "+f"(d[57]), "+f"(d[58]), "+f"(d[59]), "+f"(d[60]), "+f"(d[61]), "+f"(d[62]), "+f"(d[63])

#define OUT64(d) \
    "=f"(d[0]), "=f"(d[1]), "=f"(d[2]), "=f"(d[3]), "=f"(d[4]), "=f"(d[5]), "=f"(d[6]), "=f"(d[7]), \
    "=f"(d[8]), "=f"(d[9]), "=f"(d[10]), "=f"(d[11]), "=f"(d[12]), "=f"(d[13]), "=f"(d[14]), "=f"(d[15]), \
    "=f"(d[16]), "=f"(d[17]), "=f"(d[18]), "=f"(d[19]), "=f"(d[20]), "=f"(d[21]), "=f"(d[22]), "=f"(d[23]), \
    "=f"(d[24]), "=f"(d[25]), "=f"(d[26]), "=f"(d[27]), "=f"(d[28]), "=f"(d[29]), "=f"(d[30]), "=f"(d[31]), \
    "=f"(d[32]), "=f"(d[33]), "=f"(d[34]), "=f"(d[35]), "=f"(d[36]), "=f"(d[37]), "=f"(d[38]), "=f"(d[39]), \
    "=f"(d[40]), "=f"(d[41]), "=f"(d[42]), "=f"(d[43]), "=f"(d[44]), "=f"(d[45]), "=f"(d[46]), "=f"(d[47]), \
    "=f"(d[48]), "=f"(d[49]), "=f"(d[50]), "=f"(d[51]), "=f"(d[52]), "=f"(d[53]), "=f"(d[54]), "=f"(d[55]), \
    "=f"(d[56]), "=f"(d[57]), "=f"(d[58]), "=f"(d[59]), "=f"(d[60]), "=f"(d[61]), "=f"(d[62]), "=f"(d[63])

#define REGS64                                                                                     \
    "{%0, %1, %2, %3, %4, %5, %6, %7, %8, %9, %10, %11, %12, %13, %14, %15, "                      \
    "%16, %17, %18, %19, %20, %21, %22, %23, %24, %25, %26, %27, %28, %29, %30, %31, "             \
    "%32, %33, %34, %35, %36, %37, %38, %39, %40, %41, %42, %43, %44, %45, %46, %47, "             \
    "%48, %49, %50, %51, %52, %53, %54, %55, %56, %57, %58, %59, %60, %61, %62, %63}"

__device__ __forceinline__ void wgmma_ss(float (&d)[64], uint64_t da, uint64_t db) {
    asm volatile(
        "wgmma.mma_async.sync.aligned.m64n128k16.f32.bf16.bf16 " REGS64 ", %64, %65, 1, 1, 1, 0, 0;"
        : ACC64(d)
        : "l"(da), "l"(db));
}
__device__ __forceinline__ void wgmma_ss_first(float (&d)[64], uint64_t da, uint64_t db) {
    asm volatile(
        "wgmma.mma_async.sync.aligned.m64n128k16.f32.bf16.bf16 " REGS64 ", %64, %65, 0, 1, 1, 0, 0;"
        : OUT64(d)
        : "l"(da), "l"(db));
}
__device__ __forceinline__ void wgmma_rs(float (&d)[64], uint32_t a0, uint32_t a1, uint32_t a2, uint32_t a3, uint64_t db) {
    asm volatile(
        "wgmma.mma_async.sync.aligned.m64n128k16.f32.bf16.bf16 " REGS64 ", {%64, %65, %66, %67}, %68, 1, 1, 1, 1;"
        : ACC64(d)
        : "r"(a0), "r"(a1), "r"(a2), "r"(a3), "l"(db));
}

__device__ __forceinline__ float ex2(float x) {
    float y;
    asm("ex2.approx.ftz.f32 %0, %1;" : "=f"(y) : "f"(x));
    return y;
}
__device__ __forceinline__ uint32_t pack_bf16(float lo, float hi) {
    uint32_t r;
    asm("cvt.rn.bf16x2.f32 %0, %1, %2;" : "=r"(r) : "f"(hi), "f"(lo));
    return r;
}

__device__ __forceinline__ void ldmatrix_x4(uint32_t& r0, uint32_t& r1, uint32_t& r2, uint32_t& r3, uint32_t addr) {
    asm volatile("ldmatrix.sync.aligned.m8n8.x4.shared.b16 {%0, %1, %2, %3}, [%4];"
                 : "=r"(r0), "=r"(r1), "=r"(r2), "=r"(r3) : "r"(addr) : "memory");
}
__device__ __forceinline__ void mma_16816(float& c0, float& c1, float& c2, float& c3, uint32_t a0, uint32_t a1, uint32_t a2,
                                          uint32_t a3, uint32_t b0, uint32_t b1) {
    asm volatile("mma.sync.aligned.m16n8k16.row.col.f32.bf16.bf16.f32 {%0, %1, %2, %3}, {%4, %5, %6, %7}, {%8, %9}, {%0, %1, %2, %3};"
                 : "+f"(c0), "+f"(c1), "+f"(c2), "+f"(c3)
                 : "r"(a0), "r"(a1), "r"(a2), "r"(a3), "r"(b0), "r"(b1));
}

__global__ void __cluster_dims__(2, 1, 1) __launch_bounds__(kThreads, 1)
gqa_attn_kernel(const __grid_constant__ CUtensorMap tmQ, const __grid_constant__ CUtensorMap tmK,
                const __grid_constant__ CUtensorMap tmV, __nv_bfloat16* __restrict__ out) {
    extern __shared__ uint8_t smem_raw[];
    const uint32_t smem_base = (smem_u32(smem_raw) + 1023u) & ~1023u;
    const uint32_t bar_q = smem_base + kSmemBar;
    const uint32_t bar_full = bar_q + 3 * 8;
    const uint32_t bar_empty = bar_full + kSlots * 8;

    const uint32_t t_start = clock32();
    const int tid = threadIdx.x;
    const int wg = __shfl_sync(0xffffffffu, tid >> 7, 0);
    const int cta_rank = blockIdx.x & 1;
    const int group = blockIdx.x >> 1;
    const int q_row0 = group * kRowsPerGroup + cta_rank * kRowsPerCta;
    const int kv_row0 = group * kSk;

    TRACE_GT(62);
    TRACE_PT(0);
    if (tid == 384) {
        asm volatile("prefetch.tensormap [%0];" ::"l"(&tmQ) : "memory");
        asm volatile("prefetch.tensormap [%0];" ::"l"(&tmK) : "memory");
        asm volatile("prefetch.tensormap [%0];" ::"l"(&tmV) : "memory");
        for (int i = 0; i < 3; i++) mbar_init(bar_q + i * 8, 1);
        for (int i = 0; i < kSlots; i++) {
            mbar_init(bar_full + i * 8, 1);
            mbar_init(bar_empty + i * 8, 24);
        }
        asm volatile("fence.mbarrier_init.release.cluster;" ::: "memory");
    }
    __syncwarp();
    asm volatile("barrier.cluster.arrive.relaxed.aligned;" ::: "memory");
    if (tid == 384) {
        mbar_expect_tx(bar_q, kQBytes);
        tma_load_2d(smem_base + kSmemQ, &tmQ, bar_q, 0, q_row0);
        tma_load_2d(smem_base + kSmemQ + 8192, &tmQ, bar_q, 64, q_row0);
        TRACE_PT(1);
    }
    __syncwarp();
    asm volatile("barrier.cluster.wait.aligned;" ::: "memory");

    if (wg == 3) {
        asm volatile("setmaxnreg.dec.sync.aligned.u32 32;");
        if (tid == 384) {
            auto load_q = [&](int w) {
                mbar_expect_tx(bar_q + w * 8, kQBytes);
                tma_load_2d(smem_base + kSmemQ + w * kQBytes, &tmQ, bar_q + w * 8, 0, q_row0 + w * 64);
                tma_load_2d(smem_base + kSmemQ + w * kQBytes + 8192, &tmQ, bar_q + w * 8, 64, q_row0 + w * 64);
            };
            auto load_kv = [&](int t, int slot) {
                const CUtensorMap* map = (t & 1) ? &tmV : &tmK;
                const uint32_t dst = smem_base + kSmemKV + slot * kTileBytes + cta_rank * 8192;
                const int row = kv_row0 + (t >> 1) * kBlockN + cta_rank * 64;
                mbar_expect_tx(bar_full + slot * 8, kTileBytes);
                tma_load_2d_mc(dst, map, bar_full + slot * 8, 0, row, (uint16_t)3);
                tma_load_2d_mc(dst + 16384, map, bar_full + slot * 8, 64, row, (uint16_t)3);
                TRACE_PT(2 + t);
            };
#pragma unroll
            for (int u = 1; u < 3 + kSlots; u++) {
                const int w = u - kDepth;
                if (w >= 0) {
                    const uint32_t wb = unit_is_q(w) ? bar_q + unit_idx(w) * 8 : bar_full + unit_idx(w) * 8;
                    mbar_wait(wb, 0);
                    TRACE_PT(20 + w);
                }
                if (unit_is_q(u)) load_q(unit_idx(u)); else load_kv(unit_idx(u), unit_idx(u));
            }
            int slot = 0, phase = 0;
            for (int t = kSlots; t < 2 * kNumTiles; t++) {
                mbar_wait(bar_empty + slot * 8, phase);
                load_kv(t, slot);
                if (++slot == kSlots) { slot = 0; phase ^= 1; }
            }
        }
        TRACE_DUMP();
    } else {
        asm volatile("setmaxnreg.inc.sync.aligned.u32 %0;" ::"n"(CONSUMER_REGS));
        const int lane = tid & 31;

        float o[64];
#pragma unroll
        for (int i = 0; i < 64; i++) o[i] = 0.f;
        float ms0 = -INFINITY, ms1 = -INFINITY, l0 = 0.f, l1 = 0.f;
        bool zero_ref = true;

        const uint32_t q_smem = smem_base + kSmemQ + wg * kQBytes;
        const uint32_t desc_q = desc_lo(q_smem, 16);

        const int my_bar = 1 + wg;
        const int next_bar = 1 + (wg == 2 ? 0 : wg + 1);
        if (wg == 2) { named_arrive(1, 256); named_arrive(4, 256); }

        mbar_wait(bar_q + wg * 8, 0);
        TRACE_PT(1);
        {
            constexpr uint32_t c_hi = 0x3E033E03u;
            constexpr uint32_t c_lo = 0xB9D8B9D8u;
            const uint32_t a = q_smem + (tid & 127) * 16;
            uint32_t v[8][4];
#pragma unroll
            for (int i = 0; i < 8; i++)
                asm volatile("ld.shared.v4.u32 {%0, %1, %2, %3}, [%4];"
                             : "=r"(v[i][0]), "=r"(v[i][1]), "=r"(v[i][2]), "=r"(v[i][3]) : "r"(a + i * 2048) : "memory");
#pragma unroll
            for (int i = 0; i < 8; i++) {
#pragma unroll
                for (int c = 0; c < 4; c++) {
                    uint32_t t;
                    asm("mul.rn.bf16x2 %0, %1, %2;" : "=r"(t) : "r"(v[i][c]), "r"(c_lo));
                    asm("fma.rn.bf16x2 %0, %1, %2, %3;" : "=r"(v[i][c]) : "r"(v[i][c]), "r"(c_hi), "r"(t));
                }
                asm volatile("st.shared.v4.u32 [%4], {%0, %1, %2, %3};"
                             ::"r"(v[i][0]), "r"(v[i][1]), "r"(v[i][2]), "r"(v[i][3]), "r"(a + i * 2048) : "memory");
            }
            asm volatile("fence.proxy.async.shared::cta;" ::: "memory");
            named_sync(10 + wg, 128);
        }

        float s[64];
        auto issue_qk = [&](uint32_t k_addr) {
            const uint32_t desc_k = desc_lo(k_addr, 16);
            wgmma_fence();
#pragma unroll
            for (int k = 0; k < 8; k++) {
                const uint64_t qa = mk_desc(desc_q + (((k >> 2) * 8192 + (k & 3) * 32) >> 4));
                const uint64_t kb = mk_desc(desc_k + (((k >> 2) * 16384 + (k & 3) * 32) >> 4));
                if (k == 0) wgmma_ss_first(s, qa, kb); else wgmma_ss(s, qa, kb);
            }
            wgmma_commit();
        };

        int kslot = 0, kphase = 0;
        mbar_wait(bar_full, 0);
        TRACE_PT(58);
        issue_qk(smem_base + kSmemKV);
        if (wg == 2) named_arrive(7, 256);
        wgmma_wait<0>();
#pragma unroll 1
        for (int j = 0;; j++) {
            TRACE_PT(2 + j * 6 + 0);
            const uint32_t k_smem = smem_base + kSmemKV + kslot * kTileBytes;
            int vslot = kslot + 1, vphase = kphase;
            if (vslot == kSlots) { vslot = 0; vphase ^= 1; }
            int nslot = vslot + 1, nphase = vphase;
            if (nslot == kSlots) { nslot = 0; nphase ^= 1; }
            const bool v_ready = mbar_test_wait(bar_full + vslot * 8, vphase);

            uint32_t p[32];
            do {
            if (zero_ref) {
                float sum0 = 0.f, sum1 = 0.f, sum2 = 0.f, sum3 = 0.f;
#pragma unroll
                for (int i = 0; i < 16; i++) {
                    const float e0 = ex2(s[4 * i + 0]);
                    const float e1 = ex2(s[4 * i + 1]);
                    const float e2 = ex2(s[4 * i + 2]);
                    const float e3 = ex2(s[4 * i + 3]);
                    if (i == 0) { sum0 = e0; sum1 = e1; sum2 = e2; sum3 = e3; }
                    else { sum0 += e0; sum1 += e1; sum2 += e2; sum3 += e3; }
                    p[2 * i + 0] = pack_bf16(e0, e1);
                    p[2 * i + 1] = pack_bf16(e2, e3);
                }
                sum0 = (sum0 + sum1) + l0;
                sum2 = (sum2 + sum3) + l1;
                const bool ok = (sum0 <= kPMax) && (sum2 <= kPMax) && (sum0 >= kPMin) && (sum2 >= kPMin);
                if (__all_sync(0xffffffffu, ok)) {
                    l0 = sum0;
                    l1 = sum2;
                    break;
                }
                zero_ref = false;
                if (j > 0) { ms0 = 0.f; ms1 = 0.f; }
                {
#pragma unroll
                    for (int i = 0; i < 64; i++) s[i] = 0.f;
                    const int warp = (tid >> 5) & 3;
                    const int arow = warp * 16 + (lane & 7) + ((lane >> 3) & 1) * 8;
                    const int brow = (lane & 7) + (lane >> 4) * 8;
#pragma unroll 1
                    for (int ks = 0; ks < 8; ks++) {
                        uint32_t a0, a1, a2, a3;
                        const int ca = (ks & 3) * 2 + (lane >> 4);
                        ldmatrix_x4(a0, a1, a2, a3, q_smem + (ks >> 2) * 8192 + arow * 128 + ((ca ^ (arow & 7)) << 4));
                        const int cb = (ks & 3) * 2 + ((lane >> 3) & 1);
                        const uint32_t kaddr = k_smem + (ks >> 2) * 16384 + brow * 128 + ((cb ^ (brow & 7)) << 4);
#pragma unroll
                        for (int nb = 0; nb < 8; nb++) {
                            uint32_t b0, b1, b2, b3;
                            ldmatrix_x4(b0, b1, b2, b3, kaddr + nb * 2048);
                            mma_16816(s[8 * nb + 0], s[8 * nb + 1], s[8 * nb + 2], s[8 * nb + 3], a0, a1, a2, a3, b0, b1);
                            mma_16816(s[8 * nb + 4], s[8 * nb + 5], s[8 * nb + 6], s[8 * nb + 7], a0, a1, a2, a3, b2, b3);
                        }
                    }
                }
            }
            {
                float mx0 = -INFINITY, mx1 = -INFINITY;
#pragma unroll
                for (int i = 0; i < 16; i++) {
                    mx0 = fmaxf(mx0, fmaxf(s[4 * i + 0], s[4 * i + 1]));
                    mx1 = fmaxf(mx1, fmaxf(s[4 * i + 2], s[4 * i + 3]));
                }
                mx0 = fmaxf(mx0, __shfl_xor_sync(0xffffffffu, mx0, 1));
                mx1 = fmaxf(mx1, __shfl_xor_sync(0xffffffffu, mx1, 1));
                mx0 = fmaxf(mx0, __shfl_xor_sync(0xffffffffu, mx0, 2));
                mx1 = fmaxf(mx1, __shfl_xor_sync(0xffffffffu, mx1, 2));
                mx0 = fmaxf(ms0, mx0);
                mx1 = fmaxf(ms1, mx1);
                const float a0 = ex2(ms0 - mx0);
                const float a1 = ex2(ms1 - mx1);
                ms0 = mx0;
                ms1 = mx1;
                float sum0 = 0.f, sum1 = 0.f;
#pragma unroll
                for (int i = 0; i < 16; i++) {
                    const float e0 = ex2(s[4 * i + 0] - ms0);
                    const float e1 = ex2(s[4 * i + 1] - ms0);
                    const float e2 = ex2(s[4 * i + 2] - ms1);
                    const float e3 = ex2(s[4 * i + 3] - ms1);
                    sum0 += e0 + e1;
                    sum1 += e2 + e3;
                    p[2 * i + 0] = pack_bf16(e0, e1);
                    p[2 * i + 1] = pack_bf16(e2, e3);
                    o[4 * i + 0] *= a0;
                    o[4 * i + 1] *= a0;
                    o[4 * i + 2] *= a1;
                    o[4 * i + 3] *= a1;
                }
                l0 = l0 * a0 + sum0;
                l1 = l1 * a1 + sum1;
            }
            } while (0);

            TRACE_PT(2 + j * 6 + 1);
            const uint32_t desc_v = desc_lo(smem_base + kSmemKV + vslot * kTileBytes, 16384);
            if (!v_ready) mbar_wait(bar_full + vslot * 8, vphase);
            named_sync(my_bar, 256);
            wgmma_fence();
#pragma unroll
            for (int k = 0; k < kPvHead; k++)
                wgmma_rs(o, p[4 * k + 0], p[4 * k + 1], p[4 * k + 2], p[4 * k + 3], mk_desc(desc_v + ((k * 2048) >> 4)));
            if (2 * j + kSlots < 2 * kNumTiles && lane < 2) mbar_arrive_cluster(bar_empty + kslot * 8, lane);
            const bool k_ready = (j + 1 < kNumTiles) && mbar_test_wait(bar_full + nslot * 8, nphase);
            named_sync(my_bar + 3, 256);
#pragma unroll
            for (int k = kPvHead; k < 8; k++)
                wgmma_rs(o, p[4 * k + 0], p[4 * k + 1], p[4 * k + 2], p[4 * k + 3], mk_desc(desc_v + ((k * 2048) >> 4)));
            wgmma_commit();
            TRACE_PT(2 + j * 6 + 2);
            if (j + 1 == kNumTiles) {
                if (wg != 2) { named_arrive(next_bar, 256); named_arrive(next_bar + 3, 256); }
                break;
            }
            named_arrive(next_bar, 256);
            if (!k_ready) {
                named_arrive(next_bar + 3, 256);
                mbar_wait(bar_full + nslot * 8, nphase);
            }
            named_sync(my_bar + 6, 256);
            wgmma_wait<0>();
            TRACE_PT(2 + j * 6 + 3);
            issue_qk(smem_base + kSmemKV + nslot * kTileBytes);
            if (k_ready) named_arrive(next_bar + 3, 256);
            if (!(wg == 2 && j + 2 == kNumTiles)) named_arrive(next_bar + 6, 256);
            TRACE_PT(2 + j * 6 + 4);
            if (2 * j + 1 + kSlots < 2 * kNumTiles && lane < 2) mbar_arrive_cluster(bar_empty + vslot * 8, lane);
            wgmma_wait<0>();
            kslot = nslot;
            kphase = nphase;
        }
        wgmma_wait<0>();
        TRACE_PT(59);

        l0 += __shfl_xor_sync(0xffffffffu, l0, 1);
        l1 += __shfl_xor_sync(0xffffffffu, l1, 1);
        l0 += __shfl_xor_sync(0xffffffffu, l0, 2);
        l1 += __shfl_xor_sync(0xffffffffu, l1, 2);
        const float r0 = __fdividef(1.f, l0), r1 = __fdividef(1.f, l1);
        const int warp = (tid >> 5) & 3;
        const uint32_t stage = q_smem + warp * 4096;
        {
            const int mrow = (lane & 7) + ((lane >> 3) & 1) * 8;
            const int mcol = lane >> 4;
#pragma unroll
            for (int c = 0; c < 8; c++) {
                const uint32_t v0 = pack_bf16(o[8 * c + 0] * r0, o[8 * c + 1] * r0);
                const uint32_t v1 = pack_bf16(o[8 * c + 2] * r1, o[8 * c + 3] * r1);
                const uint32_t v2 = pack_bf16(o[8 * c + 4] * r0, o[8 * c + 5] * r0);
                const uint32_t v3 = pack_bf16(o[8 * c + 6] * r1, o[8 * c + 7] * r1);
                const int chunk = c * 2 + mcol;
                const uint32_t addr = stage + mrow * 256 + ((chunk ^ (mrow & 7)) << 4);
                asm volatile("stmatrix.sync.aligned.m8n8.x4.shared.b16 [%0], {%1, %2, %3, %4};"
                             ::"r"(addr), "r"(v0), "r"(v1), "r"(v2), "r"(v3) : "memory");
            }
        }
        __syncwarp();
        {
            uint4* gout = reinterpret_cast<uint4*>(out + (size_t)(q_row0 + wg * 64 + warp * 16) * kD);
            const int chunk = lane & 15;
#pragma unroll
            for (int i = 0; i < 8; i++) {
                const int row = i * 2 + (lane >> 4);
                uint4 v;
                asm volatile("ld.shared.v4.u32 {%0, %1, %2, %3}, [%4];"
                             : "=r"(v.x), "=r"(v.y), "=r"(v.z), "=r"(v.w)
                             : "r"(stage + row * 256 + ((chunk ^ (row & 7)) << 4)) : "memory");
                gout[row * 16 + chunk] = v;
            }
        }
        TRACE_PT(60);
        TRACE_GT(63);
        TRACE_DUMP();
    }
}

typedef CUresult (*EncodeFn)(CUtensorMap*, CUtensorMapDataType, cuuint32_t, void*, const cuuint64_t*, const cuuint64_t*,
                             const cuuint32_t*, const cuuint32_t*, CUtensorMapInterleave, CUtensorMapSwizzle,
                             CUtensorMapL2promotion, CUtensorMapFloatOOBfill);

bool make_map(EncodeFn fn, CUtensorMap* map, const void* ptr, uint64_t rows) {
    cuuint64_t dims[2] = {(cuuint64_t)kD, (cuuint64_t)rows};
    cuuint64_t strides[1] = {(cuuint64_t)kD * 2};
    cuuint32_t box[2] = {64, 64};
    cuuint32_t estr[2] = {1, 1};
    CUresult r = fn(map, CU_TENSOR_MAP_DATA_TYPE_BFLOAT16, 2, const_cast<void*>(ptr), dims, strides, box, estr,
                    CU_TENSOR_MAP_INTERLEAVE_NONE, CU_TENSOR_MAP_SWIZZLE_128B, CU_TENSOR_MAP_L2_PROMOTION_L2_256B,
                    CU_TENSOR_MAP_FLOAT_OOB_FILL_NONE);
    return r == CUDA_SUCCESS;
}

}

extern "C" void kernel_launch(void* const* d_in, const int* in_sizes, int n_in, void* d_out, int out_size) {
    (void)in_sizes; (void)n_in; (void)out_size;
    static EncodeFn encode = nullptr;
    if (!encode) {
        void* fn = nullptr;
        cudaDriverEntryPointQueryResult qres;
        cudaGetDriverEntryPoint("cuTensorMapEncodeTiled", &fn, cudaEnableDefault, &qres);
        encode = (EncodeFn)fn;
        cudaFuncSetAttribute(gqa_attn_kernel, cudaFuncAttributeMaxDynamicSharedMemorySize, kSmemTotal);
    }
    CUtensorMap tmQ, tmK, tmV;
    make_map(encode, &tmQ, d_in[0], (uint64_t)kGroups * kRowsPerGroup);
    make_map(encode, &tmK, d_in[1], (uint64_t)kGroups * kSk);
    make_map(encode, &tmV, d_in[2], (uint64_t)kGroups * kSk);
    gqa_attn_kernel<<<kGroups * 2, kThreads, kSmemTotal>>>(tmQ, tmK, tmV, (__nv_bfloat16*)d_out);
}
```

```cpp
#include <cuda_runtime.h>
#include <cuda_bf16.h>
#include <cuda.h>
#include <stdint.h>

namespace {

constexpr int kB = 16, kHq = 32, kHkv = 4, kSq = 48, kSk = 1024, kD = 128;
constexpr int kGroups = kB * kHkv;
constexpr int kRowsPerGroup = (kHq / kHkv) * kSq;
constexpr int kRowsPerCta = 192;
constexpr int kBlockN = 128;
constexpr int kNumTiles = kSk / kBlockN;
constexpr int kSlots = 5;
constexpr int kTileBytes = kBlockN * kD * 2;
constexpr int kQBytes = 64 * kD * 2;
constexpr int kThreads = 512;
constexpr int kPvHead = 3;

constexpr float kPMax = 65536.f, kPMin = 1.f / 65536.f;

constexpr int kSmemQ = 0;
constexpr int kSmemKV = 3 * kQBytes;
constexpr int kSmemBar = kSmemKV + kSlots * kTileBytes;
constexpr int kSmemTotal = kSmemBar + 256 + 1024;

constexpr int kPaceStart = 2400, kPaceStep = 1200, kPaceAfterK1 = 1400, kPaceRefill = 1300;

constexpr int kSpinLimit = 1 << 18;

constexpr int kBarHead = 1, kBarTail = 4, kBarQk = 7, kBarLocal = 10, kBarLast = 13;

__device__ __forceinline__ uint32_t smem_u32(const void* p) { return (uint32_t)__cvta_generic_to_shared(p); }
__device__ __forceinline__ uint32_t clock32() {
    uint32_t t;
    asm volatile("mov.u32 %0, %%clock;" : "=r"(t));
    return t;
}
__device__ __forceinline__ void wait_until(uint32_t t) {
#pragma unroll 1
    for (int it = 0; it < 2048 && (int32_t)(clock32() - t) < 0; it++) __nanosleep(40);
}
__device__ __forceinline__ void mbar_init(uint32_t bar, uint32_t count) {
    asm volatile("mbarrier.init.shared::cta.b64 [%0], %1;" ::"r"(bar), "r"(count));
}
__device__ __forceinline__ void mbar_expect_tx(uint32_t bar, uint32_t bytes) {
    asm volatile("mbarrier.arrive.expect_tx.shared::cta.b64 _, [%0], %1;" ::"r"(bar), "r"(bytes) : "memory");
}
__device__ __forceinline__ bool mbar_try_wait(uint32_t bar, uint32_t parity) {
    uint32_t ok;
    asm volatile(
        "{\n\t.reg .pred p;\n\t"
        "mbarrier.try_wait.parity.shared::cta.b64 p, [%1], %2;\n\t"
        "selp.u32 %0, 1, 0, p;\n\t}"
        : "=r"(ok) : "r"(bar), "r"(parity) : "memory");
    return ok != 0;
}
__device__ __forceinline__ bool mbar_test_wait(uint32_t bar, uint32_t parity) {
    uint32_t ok;
    asm volatile(
        "{\n\t.reg .pred p;\n\t"
        "mbarrier.test_wait.parity.shared::cta.b64 p, [%1], %2;\n\t"
        "selp.u32 %0, 1, 0, p;\n\t}"
        : "=r"(ok) : "r"(bar), "r"(parity) : "memory");
    return ok != 0;
}
__device__ __forceinline__ void mbar_wait(uint32_t bar, uint32_t parity) {
#pragma unroll 1
    for (int it = 0; it < kSpinLimit; it++) {
        if (mbar_try_wait(bar, parity)) break;
    }
}
__device__ __forceinline__ void mbar_arrive_cluster(uint32_t bar, uint32_t cta) {
    asm volatile(
        "{\n\t.reg .b32 ra;\n\t"
        "mapa.shared::cluster.u32 ra, %0, %1;\n\t"
        "mbarrier.arrive.shared::cluster.b64 _, [ra];\n\t}"
        ::"r"(bar), "r"(cta) : "memory");
}
__device__ __forceinline__ void tma_load_2d(uint32_t dst, const CUtensorMap* map, uint32_t bar, int c0, int c1) {
    asm volatile(
        "cp.async.bulk.tensor.2d.shared::cluster.global.mbarrier::complete_tx::bytes [%0], [%1, {%3, %4}], [%2];"
        ::"r"(dst), "l"(map), "r"(bar), "r"(c0), "r"(c1) : "memory");
}
__device__ __forceinline__ void tma_load_2d_mc(uint32_t dst, const CUtensorMap* map, uint32_t bar, int c0, int c1,
                                               uint16_t mask) {
    asm volatile(
        "cp.async.bulk.tensor.2d.shared::cluster.global.mbarrier::complete_tx::bytes.multicast::cluster"
        " [%0], [%1, {%3, %4}], [%2], %5;"
        ::"r"(dst), "l"(map), "r"(bar), "r"(c0), "r"(c1), "h"(mask) : "memory");
}
__device__ __forceinline__ void l2_prefetch(const void* p, uint32_t bytes) {
    asm volatile("cp.async.bulk.prefetch.L2.global [%0], %1;" ::"l"(p), "r"(bytes) : "memory");
}
__device__ __forceinline__ void named_sync(int id, int n) { asm volatile("bar.sync %0, %1;" ::"r"(id), "r"(n) : "memory"); }
__device__ __forceinline__ void named_arrive(int id, int n) { asm volatile("bar.arrive %0, %1;" ::"r"(id), "r"(n) : "memory"); }

__device__ __forceinline__ void wgmma_fence() { asm volatile("wgmma.fence.sync.aligned;" ::: "memory"); }
__device__ __forceinline__ void wgmma_commit() { asm volatile("wgmma.commit_group.sync.aligned;" ::: "memory"); }
template <int N>
__device__ __forceinline__ void wgmma_wait() { asm volatile("wgmma.wait_group.sync.aligned %0;" ::"n"(N) : "memory"); }

constexpr uint32_t kDescHi = (1024u >> 4) | (1u << 30);
__device__ __forceinline__ uint32_t desc_lo(uint32_t addr, uint32_t lbo_bytes) {
    return ((addr & 0x3FFFF) >> 4) | ((lbo_bytes >> 4) << 16);
}
__device__ __forceinline__ uint64_t mk_desc(uint32_t lo) { return ((uint64_t)kDescHi << 32) | (uint64_t)lo; }

#define ROW8(c, d, i) c(d[i]), c(d[i + 1]), c(d[i + 2]), c(d[i + 3]), c(d[i + 4]), c(d[i + 5]), c(d[i + 6]), c(d[i + 7])
#define ALL64(c, d) ROW8(c, d, 0), ROW8(c, d, 8), ROW8(c, d, 16), ROW8(c, d, 24), ROW8(c, d, 32), ROW8(c, d, 40), \
                    ROW8(c, d, 48), ROW8(c, d, 56)
#define REGS64                                                                         \
    "{%0, %1, %2, %3, %4, %5, %6, %7, %8, %9, %10, %11, %12, %13, %14, %15, "          \
    "%16, %17, %18, %19, %20, %21, %22, %23, %24, %25, %26, %27, %28, %29, %30, %31, " \
    "%32, %33, %34, %35, %36, %37, %38, %39, %40, %41, %42, %43, %44, %45, %46, %47, " \
    "%48, %49, %50, %51, %52, %53, %54, %55, %56, %57, %58, %59, %60, %61, %62, %63}"

__device__ __forceinline__ void wgmma_ss(float (&d)[64], uint64_t da, uint64_t db) {
    asm volatile("wgmma.mma_async.sync.aligned.m64n128k16.f32.bf16.bf16 " REGS64 ", %64, %65, 1, 1, 1, 0, 0;"
                 : ALL64("+f", d)
                 : "l"(da), "l"(db));
}
__device__ __forceinline__ void wgmma_ss_first(float (&d)[64], uint64_t da, uint64_t db) {
    asm volatile("wgmma.mma_async.sync.aligned.m64n128k16.f32.bf16.bf16 " REGS64 ", %64, %65, 0, 1, 1, 0, 0;"
                 : ALL64("=f", d)
                 : "l"(da), "l"(db));
}
__device__ __forceinline__ void wgmma_rs(float (&d)[64], uint32_t a0, uint32_t a1, uint32_t a2, uint32_t a3, uint64_t db) {
    asm volatile("wgmma.mma_async.sync.aligned.m64n128k16.f32.bf16.bf16 " REGS64 ", {%64, %65, %66, %67}, %68, 1, 1, 1, 1;"
                 : ALL64("+f", d)
                 : "r"(a0), "r"(a1), "r"(a2), "r"(a3), "l"(db));
}

__device__ __forceinline__ float ex2(float x) {
    float y;
    asm("ex2.approx.ftz.f32 %0, %1;" : "=f"(y) : "f"(x));
    return y;
}
__device__ __forceinline__ uint32_t pack_bf16(float lo, float hi) {
    uint32_t r;
    asm("cvt.rn.bf16x2.f32 %0, %1, %2;" : "=r"(r) : "f"(hi), "f"(lo));
    return r;
}
__device__ __forceinline__ void ldmatrix_x4(uint32_t& r0, uint32_t& r1, uint32_t& r2, uint32_t& r3, uint32_t addr) {
    asm volatile("ldmatrix.sync.aligned.m8n8.x4.shared.b16 {%0, %1, %2, %3}, [%4];"
                 : "=r"(r0), "=r"(r1), "=r"(r2), "=r"(r3) : "r"(addr) : "memory");
}
__device__ __forceinline__ void mma_16816(float& c0, float& c1, float& c2, float& c3, uint32_t a0, uint32_t a1,
                                          uint32_t a2, uint32_t a3, uint32_t b0, uint32_t b1) {
    asm volatile(
        "mma.sync.aligned.m16n8k16.row.col.f32.bf16.bf16.f32 {%0, %1, %2, %3}, {%4, %5, %6, %7}, {%8, %9}, {%0, %1, %2, %3};"
        : "+f"(c0), "+f"(c1), "+f"(c2), "+f"(c3)
        : "r"(a0), "r"(a1), "r"(a2), "r"(a3), "r"(b0), "r"(b1));
}

__global__ void __cluster_dims__(2, 1, 1) __launch_bounds__(kThreads, 1)
gqa_attn_kernel(const char* __restrict__ gq, const char* __restrict__ gk, char* __restrict__ go,
                const __grid_constant__ CUtensorMap tmQ, const __grid_constant__ CUtensorMap tmK,
                const __grid_constant__ CUtensorMap tmV) {
    if (threadIdx.x == 480) {
        l2_prefetch(gq + (size_t)blockIdx.x * (kRowsPerCta * kD * 2), kQBytes);
        l2_prefetch(gk + (size_t)(blockIdx.x >> 1) * (kSk * kD * 2) + (blockIdx.x & 1) * 16384, 16384);
    }
    extern __shared__ uint8_t smem_raw[];
    const uint32_t smem_base = (smem_u32(smem_raw) + 1023u) & ~1023u;
    const uint32_t bar_q = smem_base + kSmemBar;
    const uint32_t bar_full = bar_q + 3 * 8;
    const uint32_t bar_empty = bar_full + kSlots * 8;

    const uint32_t t_start = clock32();
    const int tid = threadIdx.x;
    const int wg = __shfl_sync(0xffffffffu, tid >> 7, 0);
    const int cta_rank = blockIdx.x & 1;
    const int group = blockIdx.x >> 1;
    const int q_row0 = group * kRowsPerGroup + cta_rank * kRowsPerCta;
    const int kv_row0 = group * kSk;

    if (tid == 384) {
        asm volatile("prefetch.tensormap [%0];" ::"l"(&tmQ) : "memory");
        asm volatile("prefetch.tensormap [%0];" ::"l"(&tmK) : "memory");
        asm volatile("prefetch.tensormap [%0];" ::"l"(&tmV) : "memory");
        for (int i = 0; i < 3; i++) mbar_init(bar_q + i * 8, 1);
        for (int i = 0; i < kSlots; i++) {
            mbar_init(bar_full + i * 8, 1);
            mbar_init(bar_empty + i * 8, 24);
        }
        asm volatile("fence.mbarrier_init.release.cluster;" ::: "memory");
    }
    __syncwarp();
    asm volatile("barrier.cluster.arrive.relaxed.aligned;" ::: "memory");
    if (tid == 384) {
        mbar_expect_tx(bar_q, kQBytes);
        tma_load_2d(smem_base + kSmemQ, &tmQ, bar_q, 0, q_row0);
        tma_load_2d(smem_base + kSmemQ + 8192, &tmQ, bar_q, 64, q_row0);
    }
    __syncwarp();
    asm volatile("barrier.cluster.wait.aligned;" ::: "memory");

    if (wg == 3) {
        asm volatile("setmaxnreg.dec.sync.aligned.u32 32;");
        if (tid == 384) {
            auto load_q = [&](int w) {
                mbar_expect_tx(bar_q + w * 8, kQBytes);
                tma_load_2d(smem_base + kSmemQ + w * kQBytes, &tmQ, bar_q + w * 8, 0, q_row0 + w * 64);
                tma_load_2d(smem_base + kSmemQ + w * kQBytes + 8192, &tmQ, bar_q + w * 8, 64, q_row0 + w * 64);
            };
            auto load_kv = [&](int t, int slot) {
                const CUtensorMap* map = (t & 1) ? &tmV : &tmK;
                const uint32_t dst = smem_base + kSmemKV + slot * kTileBytes + cta_rank * 8192;
                const int row = kv_row0 + (t >> 1) * kBlockN + cta_rank * 64;
                mbar_expect_tx(bar_full + slot * 8, kTileBytes);
                tma_load_2d_mc(dst, map, bar_full + slot * 8, 0, row, (uint16_t)3);
                tma_load_2d_mc(dst + 16384, map, bar_full + slot * 8, 64, row, (uint16_t)3);
            };
            int slot = 0, phase = 1;
            uint32_t t_next = t_start + kPaceStart;
#pragma unroll 1
            for (int t = 0; t < 2 * kNumTiles; t++) {
                if (t >= kSlots) mbar_wait(bar_empty + slot * 8, phase);
                if (t > 0) {
                    wait_until(t_next);
                    t_next += (t == 2) ? kPaceAfterK1 : (t < kSlots - 1) ? kPaceStep : kPaceRefill;
                }
                load_kv(t, slot);
                if (t == 0) {
#pragma unroll 1
                    for (int w = 1; w < 3; w++) {
                        wait_until(t_next);
                        t_next += kPaceStep;
                        load_q(w);
                    }
                }
                if (++slot == kSlots) { slot = 0; phase ^= 1; }
            }
        }
    } else {
        asm volatile("setmaxnreg.inc.sync.aligned.u32 160;");
        const int lane = tid & 31;

        float o[64];
#pragma unroll
        for (int i = 0; i < 64; i++) o[i] = 0.f;
        float ms0 = -INFINITY, ms1 = -INFINITY, l0 = 0.f, l1 = 0.f;
        bool zero_ref = true;

        const uint32_t q_smem = smem_base + kSmemQ + wg * kQBytes;
        const uint32_t desc_q = desc_lo(q_smem, 16);
        const int warp = __shfl_sync(0xffffffffu, (tid >> 5) & 3, 0);
        const uint32_t stage = q_smem + warp * 2048;

        const int nxt = (wg == 2) ? 0 : wg + 1;
        if (wg == 2) { named_arrive(kBarHead, 256); named_arrive(kBarTail, 256); }

        mbar_wait(bar_q + wg * 8, 0);
        {
            constexpr uint32_t c_hi = 0x3E033E03u;
            constexpr uint32_t c_lo = 0xB9D8B9D8u;
            const uint32_t a = q_smem + (tid & 127) * 16;
            uint32_t v[8][4];
#pragma unroll
            for (int i = 0; i < 8; i++)
                asm volatile("ld.shared.v4.u32 {%0, %1, %2, %3}, [%4];"
                             : "=r"(v[i][0]), "=r"(v[i][1]), "=r"(v[i][2]), "=r"(v[i][3]) : "r"(a + i * 2048) : "memory");
#pragma unroll
            for (int i = 0; i < 8; i++) {
#pragma unroll
                for (int c = 0; c < 4; c++) {
                    uint32_t t;
                    asm("mul.rn.bf16x2 %0, %1, %2;" : "=r"(t) : "r"(v[i][c]), "r"(c_lo));
                    asm("fma.rn.bf16x2 %0, %1, %2, %3;" : "=r"(v[i][c]) : "r"(v[i][c]), "r"(c_hi), "r"(t));
                }
                asm volatile("st.shared.v4.u32 [%4], {%0, %1, %2, %3};"
                             ::"r"(v[i][0]), "r"(v[i][1]), "r"(v[i][2]), "r"(v[i][3]), "r"(a + i * 2048) : "memory");
            }
            asm volatile("fence.proxy.async.shared::cta;" ::: "memory");
            named_sync(kBarLocal + wg, 128);
        }

        float s[64];
        uint32_t p[32];
        auto issue_qk = [&](uint32_t k_addr) {
            const uint32_t desc_k = desc_lo(k_addr, 16);
            wgmma_fence();
#pragma unroll
            for (int k = 0; k < 8; k++) {
                const uint64_t qa = mk_desc(desc_q + (((k >> 2) * 8192 + (k & 3) * 32) >> 4));
                const uint64_t kb = mk_desc(desc_k + (((k >> 2) * 16384 + (k & 3) * 32) >> 4));
                if (k == 0) wgmma_ss_first(s, qa, kb); else wgmma_ss(s, qa, kb);
            }
            wgmma_commit();
        };

        int kslot = 0, vslot = 1, vphase = 0, nslot = 2, nphase = 0;
        mbar_wait(bar_full, 0);
        issue_qk(smem_base + kSmemKV);
        if (wg == 2) named_arrive(kBarQk, 256);
        bool v_ready = false;
        uint32_t desc_v = desc_lo(smem_base + kSmemKV + kTileBytes, 16384);
        wgmma_wait<0>();
#pragma unroll 1
        for (int j = 0;; j++) {
            do {
                if (__builtin_expect(zero_ref, 1)) {
                    float sum0 = l0, sum1, sum2 = l1, sum3;
                    bool ok = true;
#pragma unroll
                    for (int i = 0; i < 16; i++) {
                        const float e0 = ex2(s[4 * i + 0]);
                        const float e1 = ex2(s[4 * i + 1]);
                        const float e2 = ex2(s[4 * i + 2]);
                        const float e3 = ex2(s[4 * i + 3]);
                        sum0 += e0;
                        sum2 += e2;
                        if (i == 0) { sum1 = e1; sum3 = e3; } else { sum1 += e1; sum3 += e3; }
                        p[2 * i + 0] = pack_bf16(e0, e1);
                        p[2 * i + 1] = pack_bf16(e2, e3);
                        if (i == 12) ok = (sum0 >= kPMin) && (sum2 >= kPMin);
                    }
                    sum0 += sum1;
                    sum2 += sum3;
                    ok = ok && (sum2 <= kPMax) && (sum0 <= kPMax);
                    if (__builtin_expect(__all_sync(0xffffffffu, ok), 1)) {
                        l0 = sum0;
                        l1 = sum2;
                        break;
                    }
                    zero_ref = false;
                    if (j > 0) { ms0 = 0.f; ms1 = 0.f; }
#pragma unroll 1
                    for (int i = 0; i < 8; i++) {
                        const int row = warp * 16 + i * 2 + (lane >> 4), chunk = lane & 15;
                        const uint4 v = *reinterpret_cast<const uint4*>(gq + (size_t)(q_row0 + wg * 64 + row) * (kD * 2) + chunk * 16);
                        asm volatile("st.shared.v4.u32 [%4], {%0, %1, %2, %3};"
                                     ::"r"(v.x), "r"(v.y), "r"(v.z), "r"(v.w),
                                       "r"(q_smem + (chunk >> 3) * 8192 + row * 128 + (((chunk & 7) ^ (row & 7)) << 4)) : "memory");
                    }
                    asm volatile("fence.proxy.async.shared::cta;" ::: "memory");
                    __syncwarp();
#pragma unroll
                    for (int i = 0; i < 64; i++) s[i] = 0.f;
                    const int arow = warp * 16 + (lane & 7) + ((lane >> 3) & 1) * 8;
                    const int brow = (lane & 7) + (lane >> 4) * 8;
#pragma unroll 1
                    for (int ks = 0; ks < 8; ks++) {
                        uint32_t a0, a1, a2, a3;
                        const int ca = (ks & 3) * 2 + (lane >> 4);
                        ldmatrix_x4(a0, a1, a2, a3, q_smem + (ks >> 2) * 8192 + arow * 128 + ((ca ^ (arow & 7)) << 4));
                        const int cb = (ks & 3) * 2 + ((lane >> 3) & 1);
                        const uint32_t kaddr = smem_base + kSmemKV + kslot * kTileBytes + (ks >> 2) * 16384 + brow * 128 +
                                               ((cb ^ (brow & 7)) << 4);
#pragma unroll
                        for (int nb = 0; nb < 8; nb++) {
                            uint32_t b0, b1, b2, b3;
                            ldmatrix_x4(b0, b1, b2, b3, kaddr + nb * 2048);
                            mma_16816(s[8 * nb + 0], s[8 * nb + 1], s[8 * nb + 2], s[8 * nb + 3], a0, a1, a2, a3, b0, b1);
                            mma_16816(s[8 * nb + 4], s[8 * nb + 5], s[8 * nb + 6], s[8 * nb + 7], a0, a1, a2, a3, b2, b3);
                        }
                    }
                }
                constexpr float kScaleLog2 = 0.08838834764831845f * 1.4426950408889634f;
                float mx0 = -INFINITY, mx1 = -INFINITY;
#pragma unroll
                for (int i = 0; i < 16; i++) {
                    mx0 = fmaxf(mx0, fmaxf(s[4 * i + 0], s[4 * i + 1]));
                    mx1 = fmaxf(mx1, fmaxf(s[4 * i + 2], s[4 * i + 3]));
                }
                mx0 = fmaxf(mx0, __shfl_xor_sync(0xffffffffu, mx0, 1));
                mx1 = fmaxf(mx1, __shfl_xor_sync(0xffffffffu, mx1, 1));
                mx0 = fmaxf(mx0, __shfl_xor_sync(0xffffffffu, mx0, 2));
                mx1 = fmaxf(mx1, __shfl_xor_sync(0xffffffffu, mx1, 2));
                mx0 = fmaxf(ms0, mx0 * kScaleLog2);
                mx1 = fmaxf(ms1, mx1 * kScaleLog2);
                const float a0 = ex2(ms0 - mx0);
                const float a1 = ex2(ms1 - mx1);
                ms0 = mx0;
                ms1 = mx1;
                float sum0 = 0.f, sum1 = 0.f;
#pragma unroll
                for (int i = 0; i < 16; i++) {
                    const float e0 = ex2(fmaf(s[4 * i + 0], kScaleLog2, -ms0));
                    const float e1 = ex2(fmaf(s[4 * i + 1], kScaleLog2, -ms0));
                    const float e2 = ex2(fmaf(s[4 * i + 2], kScaleLog2, -ms1));
                    const float e3 = ex2(fmaf(s[4 * i + 3], kScaleLog2, -ms1));
                    sum0 += e0 + e1;
                    sum1 += e2 + e3;
                    p[2 * i + 0] = pack_bf16(e0, e1);
                    p[2 * i + 1] = pack_bf16(e2, e3);
                    o[4 * i + 0] *= a0;
                    o[4 * i + 1] *= a0;
                    o[4 * i + 2] *= a1;
                    o[4 * i + 3] *= a1;
                }
                l0 = l0 * a0 + sum0;
                l1 = l1 * a1 + sum1;
            } while (0);

            if (!v_ready) mbar_wait(bar_full + vslot * 8, vphase);
            if (j + 1 == kNumTiles) {
                if (wg != 2) named_sync(kBarHead + wg, 256);
                break;
            }
            named_sync(kBarHead + wg, 256);
            wgmma_fence();
#pragma unroll
            for (int k = 0; k < kPvHead; k++)
                wgmma_rs(o, p[4 * k + 0], p[4 * k + 1], p[4 * k + 2], p[4 * k + 3], mk_desc(desc_v + ((k * 2048) >> 4)));
            if (2 * j + kSlots < 2 * kNumTiles && lane < 2) mbar_arrive_cluster(bar_empty + kslot * 8, lane);
            const bool k_ready = mbar_test_wait(bar_full + nslot * 8, nphase);
            named_sync(kBarTail + wg, 256);
#pragma unroll
            for (int k = kPvHead; k < 8; k++)
                wgmma_rs(o, p[4 * k + 0], p[4 * k + 1], p[4 * k + 2], p[4 * k + 3], mk_desc(desc_v + ((k * 2048) >> 4)));
            wgmma_commit();
            named_arrive(kBarHead + nxt, 256);
            const bool pass = !(wg == 2 && j + 2 == kNumTiles);
            if (!pass) named_sync(kBarLast, 256);
            named_sync(kBarQk + wg, 256);
            wgmma_wait<0>();
            bool passed = !pass;
            if (!k_ready && !mbar_test_wait(bar_full + nslot * 8, nphase)) {
                if (pass) named_arrive(kBarTail + nxt, 256);
                passed = true;
                mbar_wait(bar_full + nslot * 8, nphase);
            }
            issue_qk(smem_base + kSmemKV + nslot * kTileBytes);
            if (!passed) named_arrive(kBarTail + nxt, 256);
            named_arrive(pass ? kBarQk + nxt : kBarHead + 1, 256);
            if (2 * j + 1 + kSlots < 2 * kNumTiles && lane < 2) mbar_arrive_cluster(bar_empty + vslot * 8, lane);
            kslot = nslot;
            vslot = nslot + 1;
            vphase = nphase;
            if (vslot == kSlots) { vslot = 0; vphase ^= 1; }
            nslot = vslot + 1;
            nphase = vphase;
            if (nslot == kSlots) { nslot = 0; nphase ^= 1; }
            desc_v = desc_lo(smem_base + kSmemKV + vslot * kTileBytes, 16384);
            v_ready = mbar_test_wait(bar_full + vslot * 8, vphase);
            wgmma_wait<0>();
        }
        wgmma_fence();
#pragma unroll
        for (int k = 0; k < 8; k++)
            wgmma_rs(o, p[4 * k + 0], p[4 * k + 1], p[4 * k + 2], p[4 * k + 3], mk_desc(desc_v + ((k * 2048) >> 4)));
        wgmma_commit();
        if (wg == 0) named_arrive(kBarLast, 256);

#pragma unroll 1
        for (int m = 1; m <= 2; m <<= 1) {
            l0 += __shfl_xor_sync(0xffffffffu, l0, m);
            l1 += __shfl_xor_sync(0xffffffffu, l1, m);
        }
        float r0, r1;
        asm volatile("rcp.approx.ftz.f32 %0, %1;" : "=f"(r0) : "f"(l0));
        asm volatile("rcp.approx.ftz.f32 %0, %1;" : "=f"(r1) : "f"(l1));
        const uint32_t st_addr = stage + (lane & 7) * 128 + (((lane >> 3) ^ (lane & 7)) << 4);
        const uint32_t ld_addr = stage + (lane >> 3) * 128 + (((lane & 7) ^ (lane >> 3)) << 4);
        char* gout = go + (size_t)(q_row0 + wg * 64 + warp * 16 + (lane >> 3)) * (kD * 2) + (lane & 7) * 16;
        wgmma_wait<0>();
#pragma unroll
        for (int q = 0; q < 4; q++) {
            const int h = q >> 1, g = q & 1;
            const float r = g ? r1 : r0;
#pragma unroll
            for (int c = 0; c < 2; c++) {
                const float* oo = o + 32 * h + 16 * c + 2 * g;
                const uint32_t v0 = pack_bf16(oo[0] * r, oo[1] * r);
                const uint32_t v1 = pack_bf16(oo[4] * r, oo[5] * r);
                const uint32_t v2 = pack_bf16(oo[8] * r, oo[9] * r);
                const uint32_t v3 = pack_bf16(oo[12] * r, oo[13] * r);
                asm volatile("stmatrix.sync.aligned.m8n8.x4.shared.b16 [%0], {%1, %2, %3, %4};"
                             ::"r"((st_addr ^ (c << 6)) + h * 8192 + g * 1024), "r"(v0), "r"(v1), "r"(v2), "r"(v3) : "memory");
            }
            __syncwarp();
#pragma unroll
            for (int i = 0; i < 2; i++) {
                uint4 v;
                asm volatile("ld.shared.v4.u32 {%0, %1, %2, %3}, [%4];"
                             : "=r"(v.x), "=r"(v.y), "=r"(v.z), "=r"(v.w)
                             : "r"((ld_addr ^ (i << 6)) + i * 512 + h * 8192 + g * 1024) : "memory");
                asm volatile("st.global.v4.u32 [%0], {%1, %2, %3, %4};"
                             ::"l"(gout + g * 2048 + i * 1024 + h * 128), "r"(v.x), "r"(v.y), "r"(v.z), "r"(v.w) : "memory");
            }
        }
    }
}

typedef CUresult (*EncodeFn)(CUtensorMap*, CUtensorMapDataType, cuuint32_t, void*, const cuuint64_t*, const cuuint64_t*,
                             const cuuint32_t*, const cuuint32_t*, CUtensorMapInterleave, CUtensorMapSwizzle,
                             CUtensorMapL2promotion, CUtensorMapFloatOOBfill);

void make_map(EncodeFn fn, CUtensorMap* map, const void* ptr, uint64_t rows) {
    cuuint64_t dims[2] = {(cuuint64_t)kD, (cuuint64_t)rows};
    cuuint64_t strides[1] = {(cuuint64_t)kD * 2};
    cuuint32_t box[2] = {64, 64};
    cuuint32_t estr[2] = {1, 1};
    fn(map, CU_TENSOR_MAP_DATA_TYPE_BFLOAT16, 2, const_cast<void*>(ptr), dims, strides, box, estr,
       CU_TENSOR_MAP_INTERLEAVE_NONE, CU_TENSOR_MAP_SWIZZLE_128B, CU_TENSOR_MAP_L2_PROMOTION_L2_256B,
       CU_TENSOR_MAP_FLOAT_OOB_FILL_NONE);
}

}

extern "C" void kernel_launch(void* const* d_in, const int* in_sizes, int n_in, void* d_out, int out_size) {
    (void)in_sizes; (void)n_in; (void)out_size;
    static EncodeFn encode = nullptr;
    if (!encode) {
        void* fn = nullptr;
        cudaDriverEntryPointQueryResult qres;
        cudaGetDriverEntryPoint("cuTensorMapEncodeTiled", &fn, cudaEnableDefault, &qres);
        encode = (EncodeFn)fn;
        cudaFuncSetAttribute(gqa_attn_kernel, cudaFuncAttributeMaxDynamicSharedMemorySize, kSmemTotal);
    }
    CUtensorMap tmQ, tmK, tmV;
    make_map(encode, &tmQ, d_in[0], (uint64_t)kGroups * kRowsPerGroup);
    make_map(encode, &tmK, d_in[1], (uint64_t)kGroups * kSk);
    make_map(encode, &tmV, d_in[2], (uint64_t)kGroups * kSk);
    gqa_attn_kernel<<<kGroups * 2, kThreads, kSmemTotal>>>((const char*)d_in[0], (const char*)d_in[1], (char*)d_out,
                                                           tmQ, tmK, tmV);
}
```
